```python
import torch

def _softmax(x, axis=-1):
    return torch.softmax(x, dim=axis)
def _gelu(x):
    return torch.nn.functional.gelu(x, approximate="tanh")
def _silu(x):
    return torch.nn.functional.silu(x)
def _sigmoid(x):
    return torch.sigmoid(x)
def _layernorm(x, axis=-1, eps=1e-5):
    m = x.mean(dim=axis, keepdim=True)
    v = x.var(dim=axis, keepdim=True, unbiased=False)
    return (x - m) / torch.sqrt(v + eps)
def _scatter_add(tgt, idx, src, axis=0):
    return tgt.clone().index_add_(axis, idx, src)
def _segment_sum(src, seg, n):
    out = torch.zeros((n,) + src.shape[1:], dtype=src.dtype)
    return out.index_add_(0, seg, src)
def _pad(x, pw):
    flat = tuple(v for pair in reversed(pw) for v in pair)
    return torch.nn.functional.pad(x, flat)

kernel_name = 'standalone__kv_cache_quant_int4_int2_kv_with_per_channel_or_per_token_scales__prompt'

def setup_inputs():

    _w = (lambda a: (lambda t: t.to(torch.bfloat16) if t.is_floating_point() else t)(torch.as_tensor(a)))
    B = 1
    Sq = 2048
    Skv = 2048
    Hq = 32
    Hkv = 8
    Dh = 128
    bits = 8
    G = -1
    if G <= 0 or G >= Skv:
        G = max(1, Skv // 2)
    Skv = (Skv // G) * G
    ngk = Skv // G
    qmax = (1 << bits) - 1
    return {
        "q": _w((lambda *s: torch.randn(*s, dtype=torch.bfloat16) * 0.2)(B, Hq, Sq, Dh)),
        "qk": _w(torch.randint(0, qmax + 1, (B, Hkv, Skv, Dh)).to(torch.int32)),
        "qv": _w(torch.randint(0, qmax + 1, (B, Hkv, Skv, Dh)).to(torch.int32)),
        "k_scales": _w(torch.abs((lambda *s: torch.randn(*s, dtype=torch.bfloat16) * 0.2)(B, Hkv, ngk, Dh)) * 0.05 + 0.02),
        "k_zeros": _w((lambda *s: torch.randn(*s, dtype=torch.bfloat16) * 0.2)(B, Hkv, ngk, Dh) + float(qmax) / 2.0),
        "v_scales": _w(torch.abs((lambda *s: torch.randn(*s, dtype=torch.bfloat16) * 0.05)(B, Hkv, Skv, 1)) * 0.05 + 0.02),
        "v_zeros": _w((lambda *s: torch.randn(*s, dtype=torch.bfloat16) * 0.05)(B, Hkv, Skv, 1) + float(qmax) / 2.0),
    }

def reference(q, qk, qv, k_scales, k_zeros, v_scales, v_zeros):
    B, Hq, Sq, Dh = q.shape
    Hkv, Skv = qk.shape[1], qk.shape[2]
    ngk = k_scales.shape[2]
    G = Skv // ngk
    ks = (lambda x, n, axis: torch.repeat_interleave(x, n, dim=axis))(k_scales, G, axis=2)
    kz = (lambda x, n, axis: torch.repeat_interleave(x, n, dim=axis))(k_zeros, G, axis=2)
    k = ((lambda x, dt: x.to(dt))(qk, q.dtype) - kz) * ks
    v = ((lambda x, dt: x.to(dt))(qv, q.dtype) - v_zeros) * v_scales
    rep = Hq // Hkv
    if rep > 1:
        k = (lambda x, n, axis: torch.repeat_interleave(x, n, dim=axis))(k, rep, axis=1)
        v = (lambda x, n, axis: torch.repeat_interleave(x, n, dim=axis))(v, rep, axis=1)
    scale = float(Dh) ** -0.5
    logits = torch.einsum("bhqd,bhkd->bhqk", q, k) * scale
    p = _softmax(logits, axis=-1)
    o = torch.einsum("bhqk,bhkd->bhqd", p, v)
    return o
```

```cpp
#include <cuda_runtime.h>
#include <cuda.h>
#include <cuda_bf16.h>
#include <stdint.h>

#define SOFTMODE 2

namespace {

constexpr int HQ = 32, HKV = 8, SQ = 2048, SKV = 2048, DH = 128, GROUP = 1024;
constexpr int NKT = SKV / 128;
constexpr int TILE_BYTES = 128 * 128 * 2;
constexpr int HALF_BYTES = TILE_BYTES / 2;
constexpr int STAGES = 3;
constexpr int NCTILES = HQ * SQ / 256;

constexpr int SM_K = 0;
constexpr int SM_V = SM_K + STAGES * TILE_BYTES;
constexpr int SM_Q = SM_V + STAGES * TILE_BYTES;
constexpr int SM_BAR = SM_Q + TILE_BYTES;
constexpr int BAR_FULLK = SM_BAR;
constexpr int BAR_EMPTYK = BAR_FULLK + 8 * STAGES;
constexpr int BAR_FULLV = BAR_EMPTYK + 8 * STAGES;
constexpr int BAR_EMPTYV = BAR_FULLV + 8 * STAGES;
constexpr int BAR_FULLQ = BAR_EMPTYV + 8 * STAGES;
constexpr int BAR_EMPTYQ = BAR_FULLQ + 8;
constexpr int SMEM_BYTES = BAR_EMPTYQ + 8;

constexpr float SCALE_LOG2E = 0.08838834764831845f * 1.4426950408889634f;
constexpr float SUM_HI = 1073741824.0f;
constexpr float SUM_LO = 1.0f / 1073741824.0f;

__device__ __align__(1024) uint8_t g_K[HKV * NKT * TILE_BYTES];
__device__ __align__(1024) uint8_t g_V[HKV * NKT * TILE_BYTES];
__device__ __align__(128) uint32_t g_flags[HKV * NKT * 2];
__device__ uint32_t g_done;
constexpr int ITEMS_PER_TILE = 32;
struct TileOrder { uint8_t v[HKV * NKT]; };

__device__ __forceinline__ uint32_t smem_u32(const void* p) { return (uint32_t)__cvta_generic_to_shared(p); }
__device__ __forceinline__ void mbar_init(uint32_t bar, uint32_t count) {
    asm volatile("mbarrier.init.shared::cta.b64 [%0], %1;" ::"r"(bar), "r"(count) : "memory");
}
__device__ __forceinline__ void mbar_expect_tx(uint32_t bar, uint32_t bytes) {
    asm volatile("mbarrier.arrive.expect_tx.shared::cta.b64 _, [%0], %1;" ::"r"(bar), "r"(bytes) : "memory");
}
__device__ __forceinline__ void mbar_arrive(uint32_t bar) {
    asm volatile("mbarrier.arrive.shared::cta.b64 _, [%0];" ::"r"(bar) : "memory");
}
__device__ __forceinline__ void mbar_arrive_cluster(uint32_t bar, uint32_t cta) {
    asm volatile(
        "{\n.reg .b32 ra;\nmapa.shared::cluster.u32 ra, %0, %1;\n"
        "mbarrier.arrive.shared::cluster.b64 _, [ra];\n}\n" ::"r"(bar), "r"(cta) : "memory");
}
__device__ __forceinline__ bool mbar_try(uint32_t bar, uint32_t parity) {
    uint32_t ok;
    asm volatile(
        "{\n.reg .pred p;\nmbarrier.try_wait.parity.shared::cta.b64 p, [%1], %2;\nselp.b32 %0, 1, 0, p;\n}\n"
        : "=r"(ok) : "r"(bar), "r"(parity) : "memory");
    return ok != 0;
}
__device__ __forceinline__ bool mbar_test(uint32_t bar, uint32_t parity) {
    uint32_t ok;
    asm volatile(
        "{\n.reg .pred p;\nmbarrier.test_wait.parity.shared::cta.b64 p, [%1], %2;\nselp.b32 %0, 1, 0, p;\n}\n"
        : "=r"(ok) : "r"(bar), "r"(parity) : "memory");
    return ok != 0;
}
__device__ __forceinline__ void mbar_wait(uint32_t bar, uint32_t parity) {
    if (mbar_try(bar, parity)) return;
#pragma unroll 1
    for (uint32_t n = 0; n < (1u << 17); n++) if (mbar_try(bar, parity)) break;
}
__device__ __forceinline__ void mbar_wait_trap(uint32_t bar, uint32_t parity) {
    if (mbar_try(bar, parity)) return;
    uint32_t n = 0;
    while (!mbar_try(bar, parity)) { if (++n > (1u << 22)) __trap(); }
}
__device__ __forceinline__ void bulk_load(uint32_t dst, const void* src, uint32_t bytes, uint32_t bar) {
    asm volatile("cp.async.bulk.shared::cluster.global.mbarrier::complete_tx::bytes [%0], [%1], %2, [%3];"
                 ::"r"(dst), "l"(src), "r"(bytes), "r"(bar) : "memory");
}
__device__ __forceinline__ void bulk_store(void* dst, uint32_t src, uint32_t bytes) {
    asm volatile("cp.async.bulk.global.shared::cta.bulk_group [%0], [%1], %2;" ::"l"(dst), "r"(src), "r"(bytes) : "memory");
}
__device__ __forceinline__ void tma_load_2d(uint32_t dst, const CUtensorMap* map, int x, int y, uint32_t bar) {
    asm volatile("cp.async.bulk.tensor.2d.shared::cluster.global.mbarrier::complete_tx::bytes [%0], [%1, {%2, %3}], [%4];"
                 ::"r"(dst), "l"(map), "r"(x), "r"(y), "r"(bar) : "memory");
}
__device__ __forceinline__ void bulk_load_mc(uint32_t dst, const void* src, uint32_t bytes, uint32_t bar, uint16_t mask) {
    asm volatile("cp.async.bulk.shared::cluster.global.mbarrier::complete_tx::bytes.multicast::cluster [%0], [%1], %2, [%3], %4;"
                 ::"r"(dst), "l"(src), "r"(bytes), "r"(bar), "h"(mask) : "memory");
}
__device__ __forceinline__ void bar_sync(int id, int n) { asm volatile("bar.sync %0, %1;" ::"r"(id), "r"(n) : "memory"); }
__device__ __forceinline__ void bar_arrive(int id, int n) { asm volatile("bar.arrive %0, %1;" ::"r"(id), "r"(n) : "memory"); }
__device__ __forceinline__ void cluster_sync() {
    asm volatile("barrier.cluster.arrive.relaxed.aligned;\nbarrier.cluster.wait.aligned;" ::: "memory");
}
__device__ __forceinline__ void wg_fence() { asm volatile("wgmma.fence.sync.aligned;" ::: "memory"); }
__device__ __forceinline__ void wg_commit() { asm volatile("wgmma.commit_group.sync.aligned;" ::: "memory"); }
template <int N> __device__ __forceinline__ void wg_wait() { asm volatile("wgmma.wait_group.sync.aligned %0;" ::"n"(N) : "memory"); }
template <int M> __device__ __forceinline__ void pin(float (&d)[M]) {
#pragma unroll
    for (int i = 0; i < M; i++) asm volatile("" : "+f"(d[i])::"memory");
}
template <int M> __device__ __forceinline__ void pin(uint32_t (&d)[M]) {
#pragma unroll
    for (int i = 0; i < M; i++) asm volatile("" : "+r"(d[i])::"memory");
}
__device__ __forceinline__ float ex2(float x) { float y; asm("ex2.approx.ftz.f32 %0, %1;" : "=f"(y) : "f"(x)); return y; }
__device__ __forceinline__ uint32_t pack_bf16(float lo, float hi) {
    uint32_t r; asm("cvt.rn.bf16x2.f32 %0, %1, %2;" : "=r"(r) : "f"(hi), "f"(lo)); return r;
}
__device__ __forceinline__ uint32_t bf2_sub(uint32_t a, uint32_t b) {
    uint32_t r; asm("sub.rn.bf16x2 %0, %1, %2;" : "=r"(r) : "r"(a), "r"(b)); return r;
}
__device__ __forceinline__ uint32_t bf2_mul(uint32_t a, uint32_t b) {
    uint32_t r; asm("mul.rn.bf16x2 %0, %1, %2;" : "=r"(r) : "r"(a), "r"(b)); return r;
}
__device__ __forceinline__ uint64_t make_desc(uint32_t addr, uint32_t lbo, uint32_t sbo) {
    return (uint64_t)((addr & 0x3FFFF) >> 4) | ((uint64_t)(lbo >> 4) << 16) | ((uint64_t)(sbo >> 4) << 32) | (1ull << 62);
}

__device__ __forceinline__ void wgmma_n128_rs_kmajor(float (&d)[64], uint32_t a0, uint32_t a1, uint32_t a2, uint32_t a3, uint64_t descB, int scaleD) {
    asm volatile(
        "{\n.reg .pred p;\nsetp.ne.b32 p, %69, 0;\n"
        "wgmma.mma_async.sync.aligned.m64n128k16.f32.bf16.bf16 "
        "{%0, %1, %2, %3, %4, %5, %6, %7, %8, %9, %10, %11, %12, %13, %14, %15, "
        "%16, %17, %18, %19, %20, %21, %22, %23, %24, %25, %26, %27, %28, %29, %30, %31, "
        "%32, %33, %34, %35, %36, %37, %38, %39, %40, %41, %42, %43, %44, %45, %46, %47, "
        "%48, %49, %50, %51, %52, %53, %54, %55, %56, %57, %58, %59, %60, %61, %62, %63}, "
        "{%64, %65, %66, %67}, %68, p, 1, 1, 0;\n}\n"
        : "+f"(d[0]), "+f"(d[1]), "+f"(d[2]), "+f"(d[3]), "+f"(d[4]), "+f"(d[5]), "+f"(d[6]), "+f"(d[7]),
          "+f"(d[8]), "+f"(d[9]), "+f"(d[10]), "+f"(d[11]), "+f"(d[12]), "+f"(d[13]), "+f"(d[14]), "+f"(d[15]),
          "+f"(d[16]), "+f"(d[17]), "+f"(d[18]), "+f"(d[19]), "+f"(d[20]), "+f"(d[21]), "+f"(d[22]), "+f"(d[23]),
          "+f"(d[24]), "+f"(d[25]), "+f"(d[26]), "+f"(d[27]), "+f"(d[28]), "+f"(d[29]), "+f"(d[30]), "+f"(d[31]),
          "+f"(d[32]), "+f"(d[33]), "+f"(d[34]), "+f"(d[35]), "+f"(d[36]), "+f"(d[37]), "+f"(d[38]), "+f"(d[39]),
          "+f"(d[40]), "+f"(d[41]), "+f"(d[42]), "+f"(d[43]), "+f"(d[44]), "+f"(d[45]), "+f"(d[46]), "+f"(d[47]),
          "+f"(d[48]), "+f"(d[49]), "+f"(d[50]), "+f"(d[51]), "+f"(d[52]), "+f"(d[53]), "+f"(d[54]), "+f"(d[55]),
          "+f"(d[56]), "+f"(d[57]), "+f"(d[58]), "+f"(d[59]), "+f"(d[60]), "+f"(d[61]), "+f"(d[62]), "+f"(d[63])
        : "r"(a0), "r"(a1), "r"(a2), "r"(a3), "l"(descB), "r"(scaleD));
}
__device__ __forceinline__ void wgmma_n128_rs_mnmajor(float (&d)[64], uint32_t a0, uint32_t a1, uint32_t a2, uint32_t a3, uint64_t descB, int scaleD) {
    asm volatile(
        "{\n.reg .pred p;\nsetp.ne.b32 p, %69, 0;\n"
        "wgmma.mma_async.sync.aligned.m64n128k16.f32.bf16.bf16 "
        "{%0, %1, %2, %3, %4, %5, %6, %7, %8, %9, %10, %11, %12, %13, %14, %15, "
        "%16, %17, %18, %19, %20, %21, %22, %23, %24, %25, %26, %27, %28, %29, %30, %31, "
        "%32, %33, %34, %35, %36, %37, %38, %39, %40, %41, %42, %43, %44, %45, %46, %47, "
        "%48, %49, %50, %51, %52, %53, %54, %55, %56, %57, %58, %59, %60, %61, %62, %63}, "
        "{%64, %65, %66, %67}, %68, p, 1, 1, 1;\n}\n"
        : "+f"(d[0]), "+f"(d[1]), "+f"(d[2]), "+f"(d[3]), "+f"(d[4]), "+f"(d[5]), "+f"(d[6]), "+f"(d[7]),
          "+f"(d[8]), "+f"(d[9]), "+f"(d[10]), "+f"(d[11]), "+f"(d[12]), "+f"(d[13]), "+f"(d[14]), "+f"(d[15]),
          "+f"(d[16]), "+f"(d[17]), "+f"(d[18]), "+f"(d[19]), "+f"(d[20]), "+f"(d[21]), "+f"(d[22]), "+f"(d[23]),
          "+f"(d[24]), "+f"(d[25]), "+f"(d[26]), "+f"(d[27]), "+f"(d[28]), "+f"(d[29]), "+f"(d[30]), "+f"(d[31]),
          "+f"(d[32]), "+f"(d[33]), "+f"(d[34]), "+f"(d[35]), "+f"(d[36]), "+f"(d[37]), "+f"(d[38]), "+f"(d[39]),
          "+f"(d[40]), "+f"(d[41]), "+f"(d[42]), "+f"(d[43]), "+f"(d[44]), "+f"(d[45]), "+f"(d[46]), "+f"(d[47]),
          "+f"(d[48]), "+f"(d[49]), "+f"(d[50]), "+f"(d[51]), "+f"(d[52]), "+f"(d[53]), "+f"(d[54]), "+f"(d[55]),
          "+f"(d[56]), "+f"(d[57]), "+f"(d[58]), "+f"(d[59]), "+f"(d[60]), "+f"(d[61]), "+f"(d[62]), "+f"(d[63])
        : "r"(a0), "r"(a1), "r"(a2), "r"(a3), "l"(descB), "r"(scaleD));
}
__device__ __forceinline__ void wgmma_n64_rs_kmajor(float (&d)[32], uint32_t a0, uint32_t a1, uint32_t a2, uint32_t a3, uint64_t descB, int scaleD) {
    asm volatile(
        "{\n.reg .pred p;\nsetp.ne.b32 p, %37, 0;\n"
        "wgmma.mma_async.sync.aligned.m64n64k16.f32.bf16.bf16 "
        "{%0, %1, %2, %3, %4, %5, %6, %7, %8, %9, %10, %11, %12, %13, %14, %15, "
        "%16, %17, %18, %19, %20, %21, %22, %23, %24, %25, %26, %27, %28, %29, %30, %31}, "
        "{%32, %33, %34, %35}, %36, p, 1, 1, 0;\n}\n"
        : "+f"(d[0]), "+f"(d[1]), "+f"(d[2]), "+f"(d[3]), "+f"(d[4]), "+f"(d[5]), "+f"(d[6]), "+f"(d[7]),
          "+f"(d[8]), "+f"(d[9]), "+f"(d[10]), "+f"(d[11]), "+f"(d[12]), "+f"(d[13]), "+f"(d[14]), "+f"(d[15]),
          "+f"(d[16]), "+f"(d[17]), "+f"(d[18]), "+f"(d[19]), "+f"(d[20]), "+f"(d[21]), "+f"(d[22]), "+f"(d[23]),
          "+f"(d[24]), "+f"(d[25]), "+f"(d[26]), "+f"(d[27]), "+f"(d[28]), "+f"(d[29]), "+f"(d[30]), "+f"(d[31])
        : "r"(a0), "r"(a1), "r"(a2), "r"(a3), "l"(descB), "r"(scaleD));
}

template <int NR> struct RawRows { int v[4 * NR]; uint32_t s[NR / 2], z[NR / 2]; };

template <int NR>
__device__ __forceinline__ void load_k_rows(RawRows<NR>& R, const int* __restrict__ qk, const __nv_bfloat16* __restrict__ ks,
                                            const __nv_bfloat16* __restrict__ kz, int head, int tile, int row0, int lane) {
    const int4* src = reinterpret_cast<const int4*>(qk + ((size_t)head * SKV + tile * 128 + row0) * DH) + lane;
#pragma unroll
    for (int r = 0; r < NR; r++) {
        const int4 t = __ldcs(src + r * (DH / 4));
        R.v[4 * r] = t.x; R.v[4 * r + 1] = t.y; R.v[4 * r + 2] = t.z; R.v[4 * r + 3] = t.w;
    }
    const int o = (head * (SKV / GROUP) + (tile * 128) / GROUP) * DH + 4 * lane;
    const uint2 sc = *reinterpret_cast<const uint2*>(ks + o), ze = *reinterpret_cast<const uint2*>(kz + o);
    R.s[0] = sc.x; R.s[1] = sc.y; R.z[0] = ze.x; R.z[1] = ze.y;
}
template <int NR>
__device__ __forceinline__ uint2 convert_k_row(const RawRows<NR>& R, int r) {
    uint32_t a = pack_bf16((float)R.v[4 * r], (float)R.v[4 * r + 1]), c = pack_bf16((float)R.v[4 * r + 2], (float)R.v[4 * r + 3]);
    a = bf2_mul(bf2_sub(a, R.z[0]), R.s[0]);
    c = bf2_mul(bf2_sub(c, R.z[1]), R.s[1]);
    a = pack_bf16(__uint_as_float(a << 16) * SCALE_LOG2E, __uint_as_float(a & 0xffff0000u) * SCALE_LOG2E);
    c = pack_bf16(__uint_as_float(c << 16) * SCALE_LOG2E, __uint_as_float(c & 0xffff0000u) * SCALE_LOG2E);
    return make_uint2(a, c);
}
__device__ __forceinline__ uint32_t k_row_offset(int row, int lane) {
    return (lane >> 4) * HALF_BYTES + row * 128 + ((((lane >> 1) & 7) ^ (row & 7)) << 4) + (lane & 1) * 8;
}
template <int NR>
__device__ __forceinline__ void load_v_rows(RawRows<NR>& R, const int* __restrict__ qv, const __nv_bfloat16* __restrict__ vs,
                                            const __nv_bfloat16* __restrict__ vz, int head, int tile, int row0, int lane) {
    const int tok0 = head * SKV + tile * 128 + row0 + (lane >> 4);
    const int2* src = reinterpret_cast<const int2*>(qv + (size_t)tok0 * DH + 32 * ((lane >> 2) & 3) + 2 * (lane & 3));
#pragma unroll
    for (int r = 0; r < NR / 2; r++) {
#pragma unroll
        for (int j = 0; j < 4; j++) {
            const int2 t = __ldcs(src + r * 2 * (DH / 2) + j * 4);
            R.v[8 * r + 2 * j] = t.x; R.v[8 * r + 2 * j + 1] = t.y;
        }
        R.s[r] = __bfloat16_as_ushort(vs[tok0 + r * 2]);
        R.z[r] = __bfloat16_as_ushort(vz[tok0 + r * 2]);
    }
}
template <int NR>
__device__ __forceinline__ uint4 convert_v_row(const RawRows<NR>& R, int r) {
    const uint32_t s = R.s[r] | (R.s[r] << 16), z = R.z[r] | (R.z[r] << 16);
    uint32_t w[4];
#pragma unroll
    for (int j = 0; j < 4; j++) w[j] = bf2_mul(bf2_sub(pack_bf16((float)R.v[8 * r + 2 * j], (float)R.v[8 * r + 2 * j + 1]), z), s);
    return make_uint4(w[0], w[1], w[2], w[3]);
}
__device__ __forceinline__ uint32_t v_row_offset(int row, int lane) {
    const int c = (lane >> 2) & 3, chunk = 4 * (c & 1) + (lane & 3);
    return (c >> 1) * HALF_BYTES + row * 128 + ((chunk ^ (row & 7)) << 4);
}

struct DequantArgs {
    const int* qk; const int* qv;
    const __nv_bfloat16* ks; const __nv_bfloat16* kz; const __nv_bfloat16* vs; const __nv_bfloat16* vz;
};
template <int NR>
__device__ __forceinline__ void dequant_worker(const DequantArgs& A, const TileOrder& order, int pair0, int first, int last, int step,
                                               int lane) {
    constexpr int IPT = 128 / NR;
    RawRows<NR> R;
    auto load_item = [&](int item) {
        const int ht = order.v[pair0 + item / (2 * IPT)], row0 = (item % IPT) * NR;
        if ((item / IPT) & 1) load_v_rows<NR>(R, A.qv, A.vs, A.vz, ht >> 4, ht & 15, row0, lane);
        else load_k_rows<NR>(R, A.qk, A.ks, A.kz, ht >> 4, ht & 15, row0, lane);
    };
    int item = first;
    if (item < last) load_item(item);
    while (item < last) {
        const int ht = order.v[pair0 + item / (2 * IPT)], isv = (item / IPT) & 1, row0 = (item % IPT) * NR;
        if (isv) {
            uint8_t* dst = g_V + (size_t)ht * TILE_BYTES;
#pragma unroll
            for (int r = 0; r < NR / 2; r++)
                *reinterpret_cast<uint4*>(dst + v_row_offset(row0 + r * 2 + (lane >> 4), lane)) = convert_v_row<NR>(R, r);
        } else {
            uint8_t* dst = g_K + (size_t)ht * TILE_BYTES;
#pragma unroll
            for (int r = 0; r < NR; r++)
                *reinterpret_cast<uint2*>(dst + k_row_offset(row0 + r, lane)) = convert_k_row<NR>(R, r);
        }
        item += step;
        if (item < last) load_item(item);
        __syncwarp();
        if (lane == 0)
            asm volatile("red.release.gpu.global.add.u32 [%0], %1;" ::"l"(g_flags + ht * 2 + isv), "r"(NR / 4) : "memory");
    }
}

constexpr int DQ_RAW = 0;
constexpr int DQ_OUT = 2 * 65536;
constexpr int DQ_SC = DQ_OUT + 2 * TILE_BYTES;
constexpr int DQ_BAR = DQ_SC + 2 * 512;
static_assert(DQ_BAR + 64 <= SMEM_BYTES, "dequant staging must fit");

__device__ __forceinline__ void dequant_cta(const DequantArgs& A, const TileOrder& order, uint8_t* smem, uint32_t sb, int first,
                                            int step, int warp, int lane) {
    constexpr int NT = HKV * NKT * 2;
    const uint32_t rawfull = sb + DQ_BAR, rawempty = rawfull + 16, outfull = rawfull + 32, outempty = rawfull + 48;
    if (threadIdx.x == 0) {
        for (int s = 0; s < 2; s++) {
            mbar_init(rawfull + 8 * s, 1);
            mbar_init(rawempty + 8 * s, 8);
            mbar_init(outfull + 8 * s, 8);
            mbar_init(outempty + 8 * s, 1);
        }
        asm volatile("fence.mbarrier_init.release.cluster;" ::: "memory");
    }
    __syncthreads();
    if (warp == 0) {
        if (lane == 0) {
            uint32_t n = 0;
            for (int q = first; q < NT; q += step, n++) {
                const int s = n & 1, ht = order.v[q >> 1];
                mbar_wait_trap(rawempty + 8 * s, ((n >> 1) & 1) ^ 1);
                const size_t tok = (size_t)(ht >> 4) * SKV + (ht & 15) * 128;
                const uint8_t* src = reinterpret_cast<const uint8_t*>(((q & 1) ? A.qv : A.qk) + tok * DH);
                mbar_expect_tx(rawfull + 8 * s, 65536 + ((q & 1) ? 512 : 0));
#pragma unroll
                for (int i = 0; i < 4; i++) bulk_load(sb + DQ_RAW + s * 65536 + i * 16384, src + i * 16384, 16384, rawfull + 8 * s);
                if (q & 1) {
                    bulk_load(sb + DQ_SC + s * 512, A.vs + tok, 256, rawfull + 8 * s);
                    bulk_load(sb + DQ_SC + s * 512 + 256, A.vz + tok, 256, rawfull + 8 * s);
                }
            }
        }
    } else if (warp <= 2) {
        if (lane == 0) {
            const int s = warp - 1;
            uint32_t n = s;
            for (int q = first + s * step; q < NT; q += 2 * step, n += 2) {
                const int ht = order.v[q >> 1];
                mbar_wait_trap(outfull + 8 * s, (n >> 1) & 1);
                bulk_store(((q & 1) ? g_V : g_K) + (size_t)ht * TILE_BYTES, sb + DQ_OUT + s * TILE_BYTES, TILE_BYTES);
                asm volatile("cp.async.bulk.commit_group;\ncp.async.bulk.wait_group 0;" ::: "memory");
                mbar_arrive(outempty + 8 * s);
                asm volatile("red.release.gpu.global.add.u32 [%0], %1;" ::"l"(g_flags + ht * 2 + (q & 1)), "r"(ITEMS_PER_TILE) : "memory");
            }
        }
    } else if (warp >= 4) {
        const int row0 = (warp - 4) * 16;
        uint32_t n = 0;
        for (int q = first; q < NT; q += step, n++) {
            const int s = n & 1, ht = order.v[q >> 1];
            const uint8_t* raw = smem + DQ_RAW + s * 65536 + row0 * 512;
            uint8_t* dst = smem + DQ_OUT + s * TILE_BYTES;
            if (q & 1) {
                mbar_wait_trap(rawfull + 8 * s, (n >> 1) & 1);
                mbar_wait_trap(outempty + 8 * s, ((n >> 1) & 1) ^ 1);
                const uint16_t* sc = reinterpret_cast<const uint16_t*>(smem + DQ_SC + s * 512) + row0;
                const int c = lane >> 3, j = (lane >> 1) & 3, e0 = 2 * (lane & 1);
                uint8_t* base = dst + (c >> 1) * HALF_BYTES + 4 * j;
                const int chunk = 4 * (c & 1) + e0;
#pragma unroll 4
                for (int r = 0; r < 16; r++) {
                    const int4 v = *reinterpret_cast<const int4*>(raw + r * 512 + lane * 16);
                    const uint32_t s1 = sc[r], z1 = sc[128 + r];
                    const uint32_t s2 = s1 | (s1 << 16), z2 = z1 | (z1 << 16);
                    const uint32_t a = bf2_mul(bf2_sub(pack_bf16((float)v.x, (float)v.y), z2), s2);
                    const uint32_t b = bf2_mul(bf2_sub(pack_bf16((float)v.z, (float)v.w), z2), s2);
                    const int row = row0 + r;
                    *reinterpret_cast<uint32_t*>(base + row * 128 + ((chunk ^ (row & 7)) << 4)) = a;
                    *reinterpret_cast<uint32_t*>(base + row * 128 + (((chunk + 1) ^ (row & 7)) << 4)) = b;
                }
            } else {
                RawRows<4> R;
                const int o = ((ht >> 4) * (SKV / GROUP) + ((ht & 15) * 128) / GROUP) * DH + 4 * lane;
                const uint2 sc = *reinterpret_cast<const uint2*>(A.ks + o), ze = *reinterpret_cast<const uint2*>(A.kz + o);
                R.s[0] = sc.x; R.s[1] = sc.y; R.z[0] = ze.x; R.z[1] = ze.y;
                mbar_wait_trap(rawfull + 8 * s, (n >> 1) & 1);
                mbar_wait_trap(outempty + 8 * s, ((n >> 1) & 1) ^ 1);
#pragma unroll 1
                for (int r4 = 0; r4 < 16; r4 += 4) {
#pragma unroll
                    for (int r = 0; r < 4; r++) {
                        const int4 v = *reinterpret_cast<const int4*>(raw + (r4 + r) * 512 + lane * 16);
                        R.v[4 * r] = v.x; R.v[4 * r + 1] = v.y; R.v[4 * r + 2] = v.z; R.v[4 * r + 3] = v.w;
                    }
#pragma unroll
                    for (int r = 0; r < 4; r++)
                        *reinterpret_cast<uint2*>(dst + k_row_offset(row0 + r4 + r, lane)) = convert_k_row<4>(R, r);
                }
            }
            asm volatile("fence.proxy.async.shared::cta;" ::: "memory");
            __syncwarp();
            if (lane == 0) { mbar_arrive(rawempty + 8 * s); mbar_arrive(outfull + 8 * s); }
        }
    }
}

template <bool FIRST>
__device__ __forceinline__ void softmax_exact(const float (&Sa)[32], const float (&Sb)[32], uint32_t (&P)[32], float (&O)[64],
                                              float& l0, float& l1, float& m0, float& m1) {
    constexpr float c = (SOFTMODE == 2) ? 1.0f : SCALE_LOG2E;
    float x0 = fmaxf(Sa[0], Sa[1]), x1 = fmaxf(Sa[2], Sa[3]);
#pragma unroll
    for (int n = 1; n < 8; n++) {
        x0 = fmaxf(x0, fmaxf(Sa[4 * n], Sa[4 * n + 1]));
        x1 = fmaxf(x1, fmaxf(Sa[4 * n + 2], Sa[4 * n + 3]));
    }
#pragma unroll
    for (int n = 0; n < 8; n++) {
        x0 = fmaxf(x0, fmaxf(Sb[4 * n], Sb[4 * n + 1]));
        x1 = fmaxf(x1, fmaxf(Sb[4 * n + 2], Sb[4 * n + 3]));
    }
    x0 = fmaxf(x0, __shfl_xor_sync(0xffffffffu, x0, 1));
    x1 = fmaxf(x1, __shfl_xor_sync(0xffffffffu, x1, 1));
    x0 = fmaxf(x0, __shfl_xor_sync(0xffffffffu, x0, 2));
    x1 = fmaxf(x1, __shfl_xor_sync(0xffffffffu, x1, 2));
    x0 *= c; x1 *= c;
    if (FIRST) {
        m0 = x0; m1 = x1; l0 = 0.f; l1 = 0.f;
    } else {
        x0 = fmaxf(x0, m0); x1 = fmaxf(x1, m1);
        const float a0 = ex2(m0 - x0), a1 = ex2(m1 - x1);
        m0 = x0; m1 = x1; l0 *= a0; l1 *= a1;
#pragma unroll
        for (int n = 0; n < 16; n++) { O[4 * n] *= a0; O[4 * n + 1] *= a0; O[4 * n + 2] *= a1; O[4 * n + 3] *= a1; }
    }
    float s0 = 0.f, s1 = 0.f;
#pragma unroll
    for (int n = 0; n < 8; n++) {
        const float p0 = ex2(fmaf(Sa[4 * n], c, -m0)), p1 = ex2(fmaf(Sa[4 * n + 1], c, -m0));
        const float p2 = ex2(fmaf(Sa[4 * n + 2], c, -m1)), p3 = ex2(fmaf(Sa[4 * n + 3], c, -m1));
        s0 += p0 + p1; s1 += p2 + p3;
        P[2 * n] = pack_bf16(p0, p1); P[2 * n + 1] = pack_bf16(p2, p3);
    }
#pragma unroll
    for (int n = 0; n < 8; n++) {
        const float p0 = ex2(fmaf(Sb[4 * n], c, -m0)), p1 = ex2(fmaf(Sb[4 * n + 1], c, -m0));
        const float p2 = ex2(fmaf(Sb[4 * n + 2], c, -m1)), p3 = ex2(fmaf(Sb[4 * n + 3], c, -m1));
        s0 += p0 + p1; s1 += p2 + p3;
        P[16 + 2 * n] = pack_bf16(p0, p1); P[16 + 2 * n + 1] = pack_bf16(p2, p3);
    }
    l0 += s0; l1 += s1;
}

template <int PO>
__device__ __forceinline__ void softmax_fast_half(const float (&S)[32], uint32_t (&P)[32], float& a0, float& a1, float& b0,
                                                  float& b1, float m0, float m1) {
#pragma unroll
    for (int n = 0; n < 8; n++) {
        const float p0 = ex2(S[4 * n]), p1 = ex2(S[4 * n + 1]), p2 = ex2(S[4 * n + 2]), p3 = ex2(S[4 * n + 3]);
        a0 += p0; b0 += p1; a1 += p2; b1 += p3;
        P[PO + 2 * n] = pack_bf16(p0, p1); P[PO + 2 * n + 1] = pack_bf16(p2, p3);
    }
}

__device__ __forceinline__ void store_output(const float (&O)[64], float l0, float l1, __nv_bfloat16* __restrict__ out_row) {
    l0 += __shfl_xor_sync(0xffffffffu, l0, 1);
    l1 += __shfl_xor_sync(0xffffffffu, l1, 1);
    l0 += __shfl_xor_sync(0xffffffffu, l0, 2);
    l1 += __shfl_xor_sync(0xffffffffu, l1, 2);
    const float i0 = __fdividef(1.0f, l0), i1 = __fdividef(1.0f, l1);
#pragma unroll
    for (int c = 0; c < 4; c++) {
        uint4 u, w;
        u.x = pack_bf16(O[16 * c + 0] * i0, O[16 * c + 1] * i0);
        u.y = pack_bf16(O[16 * c + 4] * i0, O[16 * c + 5] * i0);
        u.z = pack_bf16(O[16 * c + 8] * i0, O[16 * c + 9] * i0);
        u.w = pack_bf16(O[16 * c + 12] * i0, O[16 * c + 13] * i0);
        w.x = pack_bf16(O[16 * c + 2] * i1, O[16 * c + 3] * i1);
        w.y = pack_bf16(O[16 * c + 6] * i1, O[16 * c + 7] * i1);
        w.z = pack_bf16(O[16 * c + 10] * i1, O[16 * c + 11] * i1);
        w.w = pack_bf16(O[16 * c + 14] * i1, O[16 * c + 15] * i1);
        *reinterpret_cast<uint4*>(out_row + 32 * c) = u;
        *reinterpret_cast<uint4*>(out_row + 8 * DH + 32 * c) = w;
    }
}

__device__ __forceinline__ void load_q_frags(uint32_t (&Q)[32], uint32_t row_addr, uint32_t swz) {
#pragma unroll
    for (int k = 0; k < 8; k++)
        asm volatile("ldmatrix.sync.aligned.m8n8.x4.shared.b16 {%0, %1, %2, %3}, [%4];"
                     : "=r"(Q[4 * k]), "=r"(Q[4 * k + 1]), "=r"(Q[4 * k + 2]), "=r"(Q[4 * k + 3])
                     : "r"(row_addr + (k >> 2) * HALF_BYTES + (swz ^ ((k & 3) << 5))) : "memory");
}

template <int HALF>
__device__ __forceinline__ void issue_qk(float (&S)[32], const uint32_t (&Q)[32], uint64_t desc) {
#pragma unroll
    for (int k = 0; k < 8; k++)
        wgmma_n64_rs_kmajor(S, Q[4 * k], Q[4 * k + 1], Q[4 * k + 2], Q[4 * k + 3],
                            desc + (uint64_t)(HALF * (8192 >> 4) + (k >> 2) * (HALF_BYTES >> 4) + (k & 3) * 2), k > 0);
}
__device__ __forceinline__ void issue_pv(float (&O)[64], const uint32_t (&P)[32], uint64_t desc, int accumulate) {
#pragma unroll
    for (int k = 0; k < 8; k++)
        wgmma_n128_rs_mnmajor(O, P[4 * k], P[4 * k + 1], P[4 * k + 2], P[4 * k + 3],
                              desc + (uint64_t)(k * (2048 >> 4)), k > 0 ? 1 : accumulate);
}

__device__ __forceinline__ int tile_row0(int ct, int rank) { return ct * 256 + rank * 128; }

__global__ void __cluster_dims__(2, 1, 1) __launch_bounds__(384, 1)
attention_kernel(const __grid_constant__ CUtensorMap qmap, const __grid_constant__ TileOrder order,
                 const __grid_constant__ DequantArgs dq, const int nclusters, const int init_pairs,
                 __nv_bfloat16* __restrict__ out) {
    extern __shared__ __align__(1024) uint8_t smem[];
    const uint32_t sb = smem_u32(smem);
    const int warp = __shfl_sync(0xffffffffu, threadIdx.x >> 5, 0), lane = threadIdx.x & 31;
    uint32_t rank;
    asm("mov.u32 %0, %%cluster_ctarank;" : "=r"(rank));
    const int cluster = blockIdx.x >> 1;
    if (cluster >= nclusters) {
        dequant_cta(dq, order, smem, sb, 2 * init_pairs + (blockIdx.x - 2 * nclusters), gridDim.x - 2 * nclusters, warp, lane);
        return;
    }
    const int ntiles = (NCTILES - cluster + nclusters - 1) / nclusters;

    if (threadIdx.x == 0) {
        if (sb & 1023) __trap();
        for (int s = 0; s < STAGES; s++) {
            mbar_init(sb + BAR_FULLK + 8 * s, 1);
            mbar_init(sb + BAR_EMPTYK + 8 * s, 4);
            mbar_init(sb + BAR_FULLV + 8 * s, 1);
            mbar_init(sb + BAR_EMPTYV + 8 * s, 4);
        }
        mbar_init(sb + BAR_FULLQ, 1);
        mbar_init(sb + BAR_EMPTYQ, 8);
        asm volatile("fence.mbarrier_init.release.cluster;" ::: "memory");
    }
    cluster_sync();

    if (warp < 4) {
        asm volatile("setmaxnreg.dec.sync.aligned.u32 40;");
        if (warp == 0) {
            uint32_t st = 0, ph = 1, qph = 1;
            auto load_q = [&](int ct) {
                mbar_wait_trap(sb + BAR_EMPTYQ, qph);
                qph ^= 1;
                if (lane == 0) {
                    mbar_expect_tx(sb + BAR_FULLQ, TILE_BYTES);
                    tma_load_2d(sb + SM_Q, &qmap, 0, tile_row0(ct, rank), sb + BAR_FULLQ);
                    tma_load_2d(sb + SM_Q + HALF_BYTES, &qmap, 64, tile_row0(ct, rank), sb + BAR_FULLQ);
                }
                __syncwarp();
            };
            uint32_t ready = 0;
            int ready_head = -1;
            auto wait_tile = [&](int head, int bit) {
                uint32_t n = 0;
                while (!((ready >> bit) & 1)) {
                    uint32_t f;
                    asm volatile("ld.acquire.gpu.global.u32 %0, [%1];" : "=r"(f) : "l"(g_flags + head * 32 + lane) : "memory");
                    ready = __ballot_sync(0xffffffffu, f == ITEMS_PER_TILE);
                    asm volatile("fence.proxy.async.global;" ::: "memory");
                    if (++n > (1u << 22)) __trap();
                }
            };
            load_q(cluster);
            for (int t = 0; t < ntiles; t++) {
                const int ct = cluster + t * nclusters;
                const int head = ct >> 5;
                if (head != ready_head) { ready = 0; ready_head = head; }
                const uint8_t* kp = g_K + (size_t)head * NKT * TILE_BYTES + rank * HALF_BYTES;
                const uint8_t* vp = g_V + (size_t)head * NKT * TILE_BYTES + rank * HALF_BYTES;
                for (int j = 0; j < NKT; j++) {
                    wait_tile(head, 2 * j);
                    mbar_wait_trap(sb + BAR_EMPTYK + 8 * st, ph);
                    if (lane == 0) {
                        mbar_expect_tx(sb + BAR_FULLK + 8 * st, TILE_BYTES);
                        bulk_load_mc(sb + SM_K + st * TILE_BYTES + rank * HALF_BYTES, kp + j * TILE_BYTES, HALF_BYTES,
                                     sb + BAR_FULLK + 8 * st, (uint16_t)3);
                    }
                    wait_tile(head, 2 * j + 1);
                    mbar_wait_trap(sb + BAR_EMPTYV + 8 * st, ph);
                    if (lane == 0) {
                        mbar_expect_tx(sb + BAR_FULLV + 8 * st, TILE_BYTES);
                        bulk_load_mc(sb + SM_V + st * TILE_BYTES + rank * HALF_BYTES, vp + j * TILE_BYTES, HALF_BYTES,
                                     sb + BAR_FULLV + 8 * st, (uint16_t)3);
                    }
                    __syncwarp();
                    if (++st == STAGES) { st = 0; ph ^= 1; }
                    if (j == 4 && t + 1 < ntiles) load_q(ct + nclusters);
                }
            }
            uint32_t ticket = 0;
            if (lane == 0) ticket = atomicAdd(&g_done, 1u);
            ticket = __shfl_sync(0xffffffffu, ticket, 0);
            if (ticket == 2 * nclusters - 1) {
#pragma unroll
                for (int i = 0; i < HKV; i++) g_flags[i * 32 + lane] = 0;
                if (lane == 0) g_done = 0;
            }
        } else {
            dequant_worker<4>(dq, order, 0, blockIdx.x * 3 + (warp - 1), init_pairs * 2 * ITEMS_PER_TILE, 2 * nclusters * 3, lane);
        }
    } else {
        asm volatile("setmaxnreg.inc.sync.aligned.u32 232;");
        const int wg = (warp >> 2) - 1, w = warp & 3;
        const int my_turn = 1 + wg, other_turn = 2 - wg;
        float O[64], Sa[32], Sb[32];
        uint32_t P[32], Q[32];
#define STAMP(i)
        float l0 = 0.f, l1 = 0.f, m0 = 0.f, m1 = 0.f;
        bool exact = false;
        uint32_t kst = 0, kph = 0, vst = 0, vph = 0, qph = 0;
        const uint64_t kdesc0 = make_desc(sb + SM_K, 16, 1024);
        const uint64_t vdesc0 = make_desc(sb + SM_V, HALF_BYTES, 1024);
        const uint32_t q_row = sb + SM_Q + (wg * 64 + w * 16 + (lane & 15)) * 128;
        const uint32_t q_swz = ((lane >> 4) ^ (lane & 7)) << 4;
        const bool releaser = (w < 2) && (lane == 0);
        const uint32_t rel_cta = rank ^ (uint32_t)w;
        const int row_in_cta = wg * 64 + w * 16 + (lane >> 2);

        auto load_q = [&]() {
            mbar_wait(sb + BAR_FULLQ, qph);
            qph ^= 1;
            load_q_frags(Q, q_row, q_swz);
            pin(Q);
            __syncwarp();
            if (lane == 0) mbar_arrive(sb + BAR_EMPTYQ);
        };
        auto release_k = [&]() {
            if (releaser) mbar_arrive_cluster(sb + BAR_EMPTYK + 8 * kst, rel_cta);
            if (++kst == STAGES) { kst = 0; kph ^= 1; }
        };
        auto release_v = [&]() {
            if (releaser) mbar_arrive_cluster(sb + BAR_EMPTYV + 8 * vst, rel_cta);
            if (++vst == STAGES) { vst = 0; vph ^= 1; }
        };
        auto softmax = [&](auto first_tag, bool next_q) {
            constexpr bool FIRST = decltype(first_tag)::value;
            float a0 = 0.f, a1 = 0.f, b0 = 0.f, b1 = 0.f;
            if (FIRST) { exact = false; if (SOFTMODE == 2) { m0 = 0.f; m1 = 0.f; l0 = 0.f; l1 = 0.f; } }
            const bool spec = !exact && !(FIRST && SOFTMODE == 1);
            if (spec) softmax_fast_half<0>(Sa, P, a0, a1, b0, b1, m0, m1);
            wg_wait<0>();
            pin(Sb); pin(Q);
            release_k();
            if (next_q) load_q();
            bool done = false;
            if (spec) {
                softmax_fast_half<16>(Sb, P, a0, a1, b0, b1, m0, m1);
                a0 += b0; a1 += b1;
                bool ok = (a0 <= SUM_HI) && (a1 <= SUM_HI);
                if (FIRST) ok = ok && (a0 >= SUM_LO) && (a1 >= SUM_LO);
                done = __all_sync(0xffffffffu, ok);
                if (done) { l0 += a0; l1 += a1; } else { exact = true; }
            }
            if (!done) softmax_exact<FIRST>(Sa, Sb, P, O, l0, l1, m0, m1);
        };
        struct True { enum { value = 1 }; };
        struct False { enum { value = 0 }; };

        if (wg == 1) bar_arrive(1, 256);
#pragma unroll
        for (int i = 0; i < 64; i++) O[i] = 0.f;

        load_q();
        mbar_wait(sb + BAR_FULLK + 8 * kst, kph);
        bar_sync(my_turn, 256);
        pin(Sa); pin(Sb); pin(Q);
        wg_fence();
        {
            const uint64_t kd = kdesc0 + (uint64_t)(kst * (TILE_BYTES >> 4));
            issue_qk<0>(Sa, Q, kd); wg_commit();
            issue_qk<1>(Sb, Q, kd); wg_commit();
        }
        bar_arrive(other_turn, 256);
        wg_wait<1>();
        pin(Sa);
        softmax(True{}, false);
        bool v_ready = false, k_ready = false;

        for (int t = 0; t < ntiles; t++) {
            const int ct = cluster + t * nclusters;
#pragma unroll 1
            for (int j = 1; j < NKT; j++) {
                STAMP(0);
                if (!v_ready) mbar_wait(sb + BAR_FULLV + 8 * vst, vph);
                if (!k_ready) mbar_wait(sb + BAR_FULLK + 8 * kst, kph);
                STAMP(1);
                bar_sync(my_turn, 256);
                STAMP(2);
                pin(Sa); pin(Sb); pin(O); pin(P); pin(Q);
                wg_fence();
                issue_pv(O, P, vdesc0 + (uint64_t)(vst * (TILE_BYTES >> 4)), j > 1);
                wg_commit();
                {
                    const uint64_t kd = kdesc0 + (uint64_t)(kst * (TILE_BYTES >> 4));
                    issue_qk<0>(Sa, Q, kd); wg_commit();
                    issue_qk<1>(Sb, Q, kd); wg_commit();
                }
                STAMP(3);
                bar_arrive(other_turn, 256);
                wg_wait<1>();
                pin(O); pin(P); pin(Sa);
                STAMP(4);
                release_v();
                {
                    const uint32_t nk = (kst + 1 == STAGES) ? 0 : kst + 1, nkph = (kst + 1 == STAGES) ? kph ^ 1 : kph;
                    v_ready = mbar_test(sb + BAR_FULLV + 8 * vst, vph);
                    k_ready = mbar_test(sb + BAR_FULLK + 8 * nk, nkph);
                }
                STAMP(5);
                softmax(False{}, j == NKT - 1 && t + 1 < ntiles);
                pin(P);
                STAMP(6);
            }
            __nv_bfloat16* out_row = out + (size_t)(tile_row0(ct, rank) + row_in_cta) * DH + 8 * (lane & 3);
            if (!v_ready) mbar_wait(sb + BAR_FULLV + 8 * vst, vph);
            if (t + 1 < ntiles) {
                if (!k_ready) mbar_wait(sb + BAR_FULLK + 8 * kst, kph);
                bar_sync(my_turn, 256);
                pin(Sa); pin(Sb); pin(O); pin(P); pin(Q);
                wg_fence();
                issue_pv(O, P, vdesc0 + (uint64_t)(vst * (TILE_BYTES >> 4)), 1);
                wg_commit();
                {
                    const uint64_t kd = kdesc0 + (uint64_t)(kst * (TILE_BYTES >> 4));
                    issue_qk<0>(Sa, Q, kd); wg_commit();
                    issue_qk<1>(Sb, Q, kd); wg_commit();
                }
                bar_arrive(other_turn, 256);
                wg_wait<2>();
                pin(O); pin(P);
                release_v();
                store_output(O, l0, l1, out_row);
                wg_wait<1>();
                pin(Sa);
                softmax(True{}, false);
                v_ready = false; k_ready = false;
            } else {
#define GST(i)
                GST(0);
                bar_sync(my_turn, 256);
                GST(1);
                pin(O); pin(P);
                wg_fence();
                issue_pv(O, P, vdesc0 + (uint64_t)(vst * (TILE_BYTES >> 4)), 1);
                wg_commit();
                if (wg == 0) bar_arrive(other_turn, 256);
                wg_wait<0>();
                pin(O); pin(P);
                GST(2);
                release_v();
                store_output(O, l0, l1, out_row);
                GST(3);
            }
        }
    }
    cluster_sync();
}

}

typedef CUresult (*EncodeTiledFn)(CUtensorMap*, CUtensorMapDataType, cuuint32_t, void*, const cuuint64_t*, const cuuint64_t*,
                                  const cuuint32_t*, const cuuint32_t*, CUtensorMapInterleave, CUtensorMapSwizzle,
                                  CUtensorMapL2promotion, CUtensorMapFloatOOBfill);

extern "C" void kernel_launch(void* const* d_in, const int* in_sizes, int n_in, void* d_out, int out_size) {
    (void)in_sizes; (void)n_in; (void)out_size;
    const int* qk = (const int*)d_in[1];
    const int* qv = (const int*)d_in[2];
    const __nv_bfloat16* ks = (const __nv_bfloat16*)d_in[3];
    const __nv_bfloat16* kz = (const __nv_bfloat16*)d_in[4];
    const __nv_bfloat16* vs = (const __nv_bfloat16*)d_in[5];
    const __nv_bfloat16* vz = (const __nv_bfloat16*)d_in[6];
    static int grid = 0, natt = 0, init_pairs = 0;
    static EncodeTiledFn encode = nullptr;
    static TileOrder order;
    if (grid == 0) {
        cudaFuncSetAttribute(attention_kernel, cudaFuncAttributeMaxDynamicSharedMemorySize, SMEM_BYTES);
        int dev = 0, sms = 0;
        cudaGetDevice(&dev);
        cudaDeviceGetAttribute(&sms, cudaDevAttrMultiProcessorCount, dev);
        int nc = sms / 2;
        {
            cudaLaunchConfig_t cfg = {};
            cfg.gridDim = dim3(2 * nc); cfg.blockDim = dim3(384); cfg.dynamicSmemBytes = SMEM_BYTES;
            cudaLaunchAttribute at[1];
            at[0].id = cudaLaunchAttributeClusterDimension;
            at[0].val.clusterDim.x = 2; at[0].val.clusterDim.y = 1; at[0].val.clusterDim.z = 1;
            cfg.attrs = at; cfg.numAttrs = 1;
            int active = 0;
            if (cudaOccupancyMaxActiveClusters(&active, attention_kernel, &cfg) == cudaSuccess && active > 1 && active < nc) nc = active;
        }
        const int waves = (NCTILES + nc - 2) / (nc - 1);
        natt = (NCTILES + waves - 1) / waves;
        grid = 2 * (nc < natt + 4 ? nc : natt + 4);
        init_pairs = (natt * 6) / (2 * ITEMS_PER_TILE);
        int n = 0;
        for (int wave = 0; wave < waves; wave++)
            for (int j = 0; j < NKT; j++)
                for (int h = 0; h < HKV; h++)
                    if ((h * (NCTILES / HKV)) / natt == wave) order.v[n++] = (uint8_t)(h * NKT + j);
        void* fn = nullptr;
        cudaDriverEntryPointQueryResult qr;
        cudaGetDriverEntryPoint("cuTensorMapEncodeTiled", &fn, cudaEnableDefault, &qr);
        encode = (EncodeTiledFn)fn;
    }
    CUtensorMap qmap;
    {
        const cuuint64_t dims[2] = {(cuuint64_t)DH, (cuuint64_t)HQ * SQ};
        const cuuint64_t strides[1] = {(cuuint64_t)DH * 2};
        const cuuint32_t box[2] = {64, 128};
        const cuuint32_t estr[2] = {1, 1};
        encode(&qmap, CU_TENSOR_MAP_DATA_TYPE_BFLOAT16, 2, d_in[0], dims, strides, box, estr, CU_TENSOR_MAP_INTERLEAVE_NONE,
               CU_TENSOR_MAP_SWIZZLE_128B, CU_TENSOR_MAP_L2_PROMOTION_L2_128B, CU_TENSOR_MAP_FLOAT_OOB_FILL_NONE);
    }
    const DequantArgs dq = {qk, qv, ks, kz, vs, vz};
    attention_kernel<<<grid, 384, SMEM_BYTES>>>(qmap, order, dq, natt, init_pairs, (__nv_bfloat16*)d_out);
}
```

```cpp
#include <cuda_runtime.h>
#include <cuda.h>
#include <cuda_bf16.h>
#include <stdint.h>

namespace {

constexpr int HQ = 32, HKV = 8, SQ = 2048, SKV = 2048, DH = 128, GROUP = 1024;
constexpr int NKT = SKV / 128;
constexpr int TILE_BYTES = 128 * 128 * 2;
constexpr int HALF_BYTES = TILE_BYTES / 2;
constexpr int STAGES = 3;
constexpr int NQT = HQ * SQ / 128;
constexpr int QT_PER_HEAD = NQT / HKV;
constexpr int NTILES = HKV * NKT * 2;

constexpr int SM_K = 0;
constexpr int SM_V = SM_K + STAGES * TILE_BYTES;
constexpr int SM_Q = SM_V + STAGES * TILE_BYTES;
constexpr int BAR_FULLK = SM_Q + TILE_BYTES;
constexpr int BAR_EMPTYK = BAR_FULLK + 8 * STAGES;
constexpr int BAR_FULLV = BAR_EMPTYK + 8 * STAGES;
constexpr int BAR_EMPTYV = BAR_FULLV + 8 * STAGES;
constexpr int BAR_FULLQ = BAR_EMPTYV + 8 * STAGES;
constexpr int BAR_EMPTYQ = BAR_FULLQ + 8;
constexpr int SMEM_BYTES = BAR_EMPTYQ + 8;
constexpr int DQ_RAW = 0;
constexpr int DQ_OUT = 2 * 65536;
constexpr int DQ_SC = DQ_OUT + 2 * TILE_BYTES;
constexpr int DQ_BAR = DQ_SC + 2 * 512;
static_assert(DQ_BAR + 80 <= SMEM_BYTES, "dequant staging must fit");

constexpr float SCALE_LOG2E = 0.08838834764831845f * 1.4426950408889634f;
constexpr float SUM_HI = 1073741824.0f;
constexpr float SUM_LO = 1.0f / 1073741824.0f;

__device__ __align__(1024) uint8_t g_K[HKV * NKT * TILE_BYTES];
__device__ __align__(1024) uint8_t g_V[HKV * NKT * TILE_BYTES];
__device__ __align__(128) uint32_t g_flags[NTILES];
__device__ uint32_t g_done;
constexpr int TILE_DONE = 32;
constexpr int HOLD_Q_ITEMS = 64;

struct TileOrder { uint8_t v[NTILES]; };
struct DequantArgs {
    const int* qk; const int* qv;
    const __nv_bfloat16* ks; const __nv_bfloat16* kz; const __nv_bfloat16* vs; const __nv_bfloat16* vz;
};

__device__ __forceinline__ uint32_t smem_u32(const void* p) { return (uint32_t)__cvta_generic_to_shared(p); }
__device__ __forceinline__ void mbar_init(uint32_t bar, uint32_t count) {
    asm volatile("mbarrier.init.shared::cta.b64 [%0], %1;" ::"r"(bar), "r"(count) : "memory");
}
__device__ __forceinline__ void mbar_expect_tx(uint32_t bar, uint32_t bytes) {
    asm volatile("mbarrier.arrive.expect_tx.shared::cta.b64 _, [%0], %1;" ::"r"(bar), "r"(bytes) : "memory");
}
__device__ __forceinline__ void mbar_arrive(uint32_t bar) {
    asm volatile("mbarrier.arrive.shared::cta.b64 _, [%0];" ::"r"(bar) : "memory");
}
__device__ __forceinline__ bool mbar_try(uint32_t bar, uint32_t parity) {
    uint32_t ok;
    asm volatile(
        "{\n.reg .pred p;\nmbarrier.try_wait.parity.shared::cta.b64 p, [%1], %2;\nselp.b32 %0, 1, 0, p;\n}\n"
        : "=r"(ok) : "r"(bar), "r"(parity) : "memory");
    return ok != 0;
}
__device__ __forceinline__ bool mbar_test(uint32_t bar, uint32_t parity) {
    uint32_t ok;
    asm volatile(
        "{\n.reg .pred p;\nmbarrier.test_wait.parity.shared::cta.b64 p, [%1], %2;\nselp.b32 %0, 1, 0, p;\n}\n"
        : "=r"(ok) : "r"(bar), "r"(parity) : "memory");
    return ok != 0;
}
__device__ __forceinline__ void mbar_wait(uint32_t bar, uint32_t parity) {
    if (mbar_try(bar, parity)) return;
#pragma unroll 1
    for (uint32_t n = 0; n < (1u << 17); n++) if (mbar_try(bar, parity)) break;
}
__device__ __forceinline__ void mbar_wait_trap(uint32_t bar, uint32_t parity) {
    if (mbar_try(bar, parity)) return;
    uint32_t n = 0;
    while (!mbar_try(bar, parity)) { if (++n > (1u << 22)) __trap(); }
}
__device__ __forceinline__ void bulk_load(uint32_t dst, const void* src, uint32_t bytes, uint32_t bar) {
    asm volatile("cp.async.bulk.shared::cluster.global.mbarrier::complete_tx::bytes [%0], [%1], %2, [%3];"
                 ::"r"(dst), "l"(src), "r"(bytes), "r"(bar) : "memory");
}
__device__ __forceinline__ void bulk_store(void* dst, uint32_t src, uint32_t bytes) {
    asm volatile("cp.async.bulk.global.shared::cta.bulk_group [%0], [%1], %2;" ::"l"(dst), "r"(src), "r"(bytes) : "memory");
}
__device__ __forceinline__ void tma_load_2d(uint32_t dst, const CUtensorMap* map, int x, int y, uint32_t bar) {
    asm volatile("cp.async.bulk.tensor.2d.shared::cluster.global.mbarrier::complete_tx::bytes [%0], [%1, {%2, %3}], [%4];"
                 ::"r"(dst), "l"(map), "r"(x), "r"(y), "r"(bar) : "memory");
}
__device__ __forceinline__ void publish(uint32_t* flag, uint32_t units) {
    asm volatile("red.release.gpu.global.add.u32 [%0], %1;" ::"l"(flag), "r"(units) : "memory");
}
__device__ __forceinline__ void bar_sync(int id, int n) { asm volatile("bar.sync %0, %1;" ::"r"(id), "r"(n) : "memory"); }
__device__ __forceinline__ void bar_arrive(int id, int n) { asm volatile("bar.arrive %0, %1;" ::"r"(id), "r"(n) : "memory"); }
__device__ __forceinline__ void wg_fence() { asm volatile("wgmma.fence.sync.aligned;" ::: "memory"); }
__device__ __forceinline__ void wg_commit() { asm volatile("wgmma.commit_group.sync.aligned;" ::: "memory"); }
template <int N> __device__ __forceinline__ void wg_wait() { asm volatile("wgmma.wait_group.sync.aligned %0;" ::"n"(N) : "memory"); }
template <int M> __device__ __forceinline__ void pin(float (&d)[M]) {
#pragma unroll
    for (int i = 0; i < M; i++) asm volatile("" : "+f"(d[i])::"memory");
}
template <int M> __device__ __forceinline__ void pin(uint32_t (&d)[M]) {
#pragma unroll
    for (int i = 0; i < M; i++) asm volatile("" : "+r"(d[i])::"memory");
}
__device__ __forceinline__ float ex2(float x) { float y; asm("ex2.approx.ftz.f32 %0, %1;" : "=f"(y) : "f"(x)); return y; }
__device__ __forceinline__ uint32_t pack_bf16(float lo, float hi) {
    uint32_t r; asm("cvt.rn.bf16x2.f32 %0, %1, %2;" : "=r"(r) : "f"(hi), "f"(lo)); return r;
}
__device__ __forceinline__ uint32_t bf2_sub(uint32_t a, uint32_t b) {
    uint32_t r; asm("sub.rn.bf16x2 %0, %1, %2;" : "=r"(r) : "r"(a), "r"(b)); return r;
}
__device__ __forceinline__ uint32_t bf2_mul(uint32_t a, uint32_t b) {
    uint32_t r; asm("mul.rn.bf16x2 %0, %1, %2;" : "=r"(r) : "r"(a), "r"(b)); return r;
}
__device__ __forceinline__ uint64_t make_desc(uint32_t addr, uint32_t lbo, uint32_t sbo) {
    return (uint64_t)((addr & 0x3FFFF) >> 4) | ((uint64_t)(lbo >> 4) << 16) | ((uint64_t)(sbo >> 4) << 32) | (1ull << 62);
}

__device__ __forceinline__ void wgmma_n128_rs_mnmajor(float (&d)[64], uint32_t a0, uint32_t a1, uint32_t a2, uint32_t a3, uint64_t descB, int scaleD) {
    asm volatile(
        "{\n.reg .pred p;\nsetp.ne.b32 p, %69, 0;\n"
        "wgmma.mma_async.sync.aligned.m64n128k16.f32.bf16.bf16 "
        "{%0, %1, %2, %3, %4, %5, %6, %7, %8, %9, %10, %11, %12, %13, %14, %15, "
        "%16, %17, %18, %19, %20, %21, %22, %23, %24, %25, %26, %27, %28, %29, %30, %31, "
        "%32, %33, %34, %35, %36, %37, %38, %39, %40, %41, %42, %43, %44, %45, %46, %47, "
        "%48, %49, %50, %51, %52, %53, %54, %55, %56, %57, %58, %59, %60, %61, %62, %63}, "
        "{%64, %65, %66, %67}, %68, p, 1, 1, 1;\n}\n"
        : "+f"(d[0]), "+f"(d[1]), "+f"(d[2]), "+f"(d[3]), "+f"(d[4]), "+f"(d[5]), "+f"(d[6]), "+f"(d[7]),
          "+f"(d[8]), "+f"(d[9]), "+f"(d[10]), "+f"(d[11]), "+f"(d[12]), "+f"(d[13]), "+f"(d[14]), "+f"(d[15]),
          "+f"(d[16]), "+f"(d[17]), "+f"(d[18]), "+f"(d[19]), "+f"(d[20]), "+f"(d[21]), "+f"(d[22]), "+f"(d[23]),
          "+f"(d[24]), "+f"(d[25]), "+f"(d[26]), "+f"(d[27]), "+f"(d[28]), "+f"(d[29]), "+f"(d[30]), "+f"(d[31]),
          "+f"(d[32]), "+f"(d[33]), "+f"(d[34]), "+f"(d[35]), "+f"(d[36]), "+f"(d[37]), "+f"(d[38]), "+f"(d[39]),
          "+f"(d[40]), "+f"(d[41]), "+f"(d[42]), "+f"(d[43]), "+f"(d[44]), "+f"(d[45]), "+f"(d[46]), "+f"(d[47]),
          "+f"(d[48]), "+f"(d[49]), "+f"(d[50]), "+f"(d[51]), "+f"(d[52]), "+f"(d[53]), "+f"(d[54]), "+f"(d[55]),
          "+f"(d[56]), "+f"(d[57]), "+f"(d[58]), "+f"(d[59]), "+f"(d[60]), "+f"(d[61]), "+f"(d[62]), "+f"(d[63])
        : "r"(a0), "r"(a1), "r"(a2), "r"(a3), "l"(descB), "r"(scaleD));
}
__device__ __forceinline__ void wgmma_n64_rs_kmajor(float (&d)[32], uint32_t a0, uint32_t a1, uint32_t a2, uint32_t a3, uint64_t descB, int scaleD) {
    asm volatile(
        "{\n.reg .pred p;\nsetp.ne.b32 p, %37, 0;\n"
        "wgmma.mma_async.sync.aligned.m64n64k16.f32.bf16.bf16 "
        "{%0, %1, %2, %3, %4, %5, %6, %7, %8, %9, %10, %11, %12, %13, %14, %15, "
        "%16, %17, %18, %19, %20, %21, %22, %23, %24, %25, %26, %27, %28, %29, %30, %31}, "
        "{%32, %33, %34, %35}, %36, p, 1, 1, 0;\n}\n"
        : "+f"(d[0]), "+f"(d[1]), "+f"(d[2]), "+f"(d[3]), "+f"(d[4]), "+f"(d[5]), "+f"(d[6]), "+f"(d[7]),
          "+f"(d[8]), "+f"(d[9]), "+f"(d[10]), "+f"(d[11]), "+f"(d[12]), "+f"(d[13]), "+f"(d[14]), "+f"(d[15]),
          "+f"(d[16]), "+f"(d[17]), "+f"(d[18]), "+f"(d[19]), "+f"(d[20]), "+f"(d[21]), "+f"(d[22]), "+f"(d[23]),
          "+f"(d[24]), "+f"(d[25]), "+f"(d[26]), "+f"(d[27]), "+f"(d[28]), "+f"(d[29]), "+f"(d[30]), "+f"(d[31])
        : "r"(a0), "r"(a1), "r"(a2), "r"(a3), "l"(descB), "r"(scaleD));
}


template <int NR> struct RawRows { int v[4 * NR]; uint32_t s[NR / 2], z[NR / 2]; };

__device__ __forceinline__ uint32_t dequant2(int a, int b, uint32_t z2, uint32_t s2) {
    return bf2_mul(bf2_sub(pack_bf16((float)a, (float)b), z2), s2);
}
__device__ __forceinline__ uint32_t fold_scale2(uint32_t k2) {
    return pack_bf16(__uint_as_float(k2 << 16) * SCALE_LOG2E, __uint_as_float(k2 & 0xffff0000u) * SCALE_LOG2E);
}
template <int NR>
__device__ __forceinline__ void load_k_scales(RawRows<NR>& R, const DequantArgs& A, int ht, int lane) {
    const int o = ((ht >> 4) * (SKV / GROUP) + ((ht & 15) * 128) / GROUP) * DH + 4 * lane;
    const uint2 sc = *reinterpret_cast<const uint2*>(A.ks + o), ze = *reinterpret_cast<const uint2*>(A.kz + o);
    R.s[0] = sc.x; R.s[1] = sc.y; R.z[0] = ze.x; R.z[1] = ze.y;
}
template <int NR>
__device__ __forceinline__ uint2 convert_k_row(const RawRows<NR>& R, int r) {
    return make_uint2(fold_scale2(dequant2(R.v[4 * r], R.v[4 * r + 1], R.z[0], R.s[0])),
                      fold_scale2(dequant2(R.v[4 * r + 2], R.v[4 * r + 3], R.z[1], R.s[1])));
}
__device__ __forceinline__ uint32_t k_row_offset(int row, int lane) {
    return (lane >> 4) * HALF_BYTES + row * 128 + ((((lane >> 1) & 7) ^ (row & 7)) << 4) + (lane & 1) * 8;
}

__device__ __forceinline__ void load_item(RawRows<4>& R, const DequantArgs& A, int f, int row0, int lane) {
    const int ht = f >> 1, tok0 = (ht >> 4) * SKV + (ht & 15) * 128 + row0;
    if (f & 1) {
        const int tok = tok0 + (lane >> 4);
        const int2* src = reinterpret_cast<const int2*>(A.qv + (size_t)tok * DH + 32 * ((lane >> 2) & 3) + 2 * (lane & 3));
#pragma unroll
        for (int r = 0; r < 2; r++) {
#pragma unroll
            for (int j = 0; j < 4; j++) {
                const int2 t = __ldcs(src + r * 2 * (DH / 2) + j * 4);
                R.v[8 * r + 2 * j] = t.x; R.v[8 * r + 2 * j + 1] = t.y;
            }
            R.s[r] = __bfloat16_as_ushort(A.vs[tok + r * 2]);
            R.z[r] = __bfloat16_as_ushort(A.vz[tok + r * 2]);
        }
    } else {
        const int4* src = reinterpret_cast<const int4*>(A.qk + (size_t)tok0 * DH) + lane;
#pragma unroll
        for (int r = 0; r < 4; r++) {
            const int4 t = __ldcs(src + r * (DH / 4));
            R.v[4 * r] = t.x; R.v[4 * r + 1] = t.y; R.v[4 * r + 2] = t.z; R.v[4 * r + 3] = t.w;
        }
        load_k_scales<4>(R, A, ht, lane);
    }
}
__device__ __forceinline__ void store_item(const RawRows<4>& R, int f, int row0, int lane) {
    const int ht = f >> 1;
    if (f & 1) {
        const int c = (lane >> 2) & 3, chunk = 4 * (c & 1) + (lane & 3);
#pragma unroll
        for (int r = 0; r < 2; r++) {
            const int row = row0 + 2 * r + (lane >> 4);
            const uint32_t s = R.s[r] | (R.s[r] << 16), z = R.z[r] | (R.z[r] << 16);
            uint4 w;
            w.x = dequant2(R.v[8 * r], R.v[8 * r + 1], z, s);
            w.y = dequant2(R.v[8 * r + 2], R.v[8 * r + 3], z, s);
            w.z = dequant2(R.v[8 * r + 4], R.v[8 * r + 5], z, s);
            w.w = dequant2(R.v[8 * r + 6], R.v[8 * r + 7], z, s);
            *reinterpret_cast<uint4*>(g_V + (size_t)ht * TILE_BYTES + (c >> 1) * HALF_BYTES + row * 128 + ((chunk ^ (row & 7)) << 4)) = w;
        }
    } else {
#pragma unroll
        for (int r = 0; r < 4; r++)
            *reinterpret_cast<uint2*>(g_K + (size_t)ht * TILE_BYTES + k_row_offset(row0 + r, lane)) = convert_k_row<4>(R, r);
    }
}

__device__ __forceinline__ void dequant_cta(const DequantArgs& A, const TileOrder& order, uint8_t* smem, uint32_t sb, int first,
                                            int step, int last, int warp, int lane) {
    const uint32_t rawfull = sb + DQ_BAR, rawempty = rawfull + 16, outempty = rawfull + 32, outfull = rawfull + 48;
    if (threadIdx.x == 0) {
        for (int s = 0; s < 2; s++) {
            mbar_init(rawfull + 8 * s, 1);
            mbar_init(rawempty + 8 * s, 8);
            mbar_init(outempty + 8 * s, 1);
            mbar_init(outfull + 8 * s, 8);
            mbar_init(outfull + 16 + 8 * s, 8);
        }
        asm volatile("fence.mbarrier_init.release.cluster;" ::: "memory");
    }
    __syncthreads();
    if (warp == 0) {
        if (lane == 0) {
            uint32_t n = 0;
            for (int q = first; q < last; q += step, n++) {
                const int s = n & 1, f = order.v[q], ht = f >> 1, isv = f & 1;
                mbar_wait_trap(rawempty + 8 * s, ((n >> 1) & 1) ^ 1);
                const size_t tok = (size_t)(ht >> 4) * SKV + (ht & 15) * 128;
                const uint8_t* src = reinterpret_cast<const uint8_t*>((isv ? A.qv : A.qk) + tok * DH);
                mbar_expect_tx(rawfull + 8 * s, 65536 + (isv ? 512 : 0));
#pragma unroll
                for (int i = 0; i < 4; i++) bulk_load(sb + DQ_RAW + s * 65536 + i * 16384, src + i * 16384, 16384, rawfull + 8 * s);
                if (isv) {
                    bulk_load(sb + DQ_SC + s * 512, A.vs + tok, 256, rawfull + 8 * s);
                    bulk_load(sb + DQ_SC + s * 512 + 256, A.vz + tok, 256, rawfull + 8 * s);
                }
            }
        }
    } else if (warp < 4) {
        if (lane == 0) {
            for (uint32_t n = warp - 1; first + (int)n * step < last; n += 3) {
                const int f = order.v[first + n * step], s = n & 1;
                mbar_wait_trap(outfull + 8 * (n & 3), (n >> 2) & 1);
                bulk_store(((f & 1) ? g_V : g_K) + (size_t)(f >> 1) * TILE_BYTES, sb + DQ_OUT + s * TILE_BYTES, TILE_BYTES);
                asm volatile("cp.async.bulk.commit_group;\ncp.async.bulk.wait_group.read 0;" ::: "memory");
                mbar_arrive(outempty + 8 * s);
                asm volatile("cp.async.bulk.wait_group 0;" ::: "memory");
                publish(g_flags + f, TILE_DONE);
            }
        }
    } else {
        const int row0 = (warp - 4) * 16;
        uint32_t n = 0;
        for (int q = first; q < last; q += step, n++) {
            const int s = n & 1, f = order.v[q];
            const uint8_t* raw = smem + DQ_RAW + s * 65536 + row0 * 512;
            uint8_t* dst = smem + DQ_OUT + s * TILE_BYTES;
            RawRows<16> R;
            if (!(f & 1)) load_k_scales<16>(R, A, f >> 1, lane);
            mbar_wait_trap(rawfull + 8 * s, (n >> 1) & 1);
#pragma unroll
            for (int r = 0; r < 16; r++) {
                const int4 v = *reinterpret_cast<const int4*>(raw + r * 512 + lane * 16);
                R.v[4 * r] = v.x; R.v[4 * r + 1] = v.y; R.v[4 * r + 2] = v.z; R.v[4 * r + 3] = v.w;
            }
            if (f & 1) {
                const uint4* sc = reinterpret_cast<const uint4*>(smem + DQ_SC + s * 512 + row0 * 2);
                const uint4 s0 = sc[0], s1 = sc[1], z0 = sc[16], z1 = sc[17];
                R.s[0] = s0.x; R.s[1] = s0.y; R.s[2] = s0.z; R.s[3] = s0.w; R.s[4] = s1.x; R.s[5] = s1.y; R.s[6] = s1.z; R.s[7] = s1.w;
                R.z[0] = z0.x; R.z[1] = z0.y; R.z[2] = z0.z; R.z[3] = z0.w; R.z[4] = z1.x; R.z[5] = z1.y; R.z[6] = z1.z; R.z[7] = z1.w;
            }
            __syncwarp();
            if (lane == 0) mbar_arrive(rawempty + 8 * s);
            mbar_wait_trap(outempty + 8 * s, ((n >> 1) & 1) ^ 1);
            if (f & 1) {
                const int c = lane >> 3, j = (lane >> 1) & 3, e0 = 2 * (lane & 1);
                uint8_t* base = dst + (c >> 1) * HALF_BYTES + 4 * j;
                const int chunk = 4 * (c & 1) + e0;
#pragma unroll
                for (int r = 0; r < 16; r++) {
                    const uint32_t s2 = __byte_perm(R.s[r >> 1], 0, (r & 1) ? 0x3232 : 0x1010);
                    const uint32_t z2 = __byte_perm(R.z[r >> 1], 0, (r & 1) ? 0x3232 : 0x1010);
                    const int row = row0 + r;
                    *reinterpret_cast<uint32_t*>(base + row * 128 + ((chunk ^ (row & 7)) << 4)) =
                        dequant2(R.v[4 * r], R.v[4 * r + 1], z2, s2);
                    *reinterpret_cast<uint32_t*>(base + row * 128 + (((chunk + 1) ^ (row & 7)) << 4)) =
                        dequant2(R.v[4 * r + 2], R.v[4 * r + 3], z2, s2);
                }
            } else {
#pragma unroll
                for (int r = 0; r < 16; r++)
                    *reinterpret_cast<uint2*>(dst + k_row_offset(row0 + r, lane)) = convert_k_row<16>(R, r);
            }
            asm volatile("fence.proxy.async.shared::cta;" ::: "memory");
            __syncwarp();
            if (lane == 0) mbar_arrive(outfull + 8 * (n & 3));
        }
    }
}


template <int PO>
__device__ __forceinline__ void softmax_fast_half(const float (&S)[32], uint32_t (&P)[32], float& a0, float& a1, float& b0,
                                                  float& b1) {
#pragma unroll
    for (int n = 0; n < 8; n++) {
        const float p0 = ex2(S[4 * n]), p1 = ex2(S[4 * n + 1]), p2 = ex2(S[4 * n + 2]), p3 = ex2(S[4 * n + 3]);
        a0 += p0; b0 += p1; a1 += p2; b1 += p3;
        P[PO + 2 * n] = pack_bf16(p0, p1); P[PO + 2 * n + 1] = pack_bf16(p2, p3);
    }
}
template <bool FIRST>
__device__ __forceinline__ void softmax_exact(const float (&Sa)[32], const float (&Sb)[32], uint32_t (&P)[32], float (&O)[64],
                                              float& l0, float& l1, float& m0, float& m1) {
    float x0 = fmaxf(Sa[0], Sa[1]), x1 = fmaxf(Sa[2], Sa[3]);
#pragma unroll
    for (int n = 1; n < 8; n++) {
        x0 = fmaxf(x0, fmaxf(Sa[4 * n], Sa[4 * n + 1]));
        x1 = fmaxf(x1, fmaxf(Sa[4 * n + 2], Sa[4 * n + 3]));
    }
#pragma unroll
    for (int n = 0; n < 8; n++) {
        x0 = fmaxf(x0, fmaxf(Sb[4 * n], Sb[4 * n + 1]));
        x1 = fmaxf(x1, fmaxf(Sb[4 * n + 2], Sb[4 * n + 3]));
    }
    x0 = fmaxf(x0, __shfl_xor_sync(0xffffffffu, x0, 1));
    x1 = fmaxf(x1, __shfl_xor_sync(0xffffffffu, x1, 1));
    x0 = fmaxf(x0, __shfl_xor_sync(0xffffffffu, x0, 2));
    x1 = fmaxf(x1, __shfl_xor_sync(0xffffffffu, x1, 2));
    if (FIRST) {
        m0 = x0; m1 = x1; l0 = 0.f; l1 = 0.f;
    } else {
        x0 = fmaxf(x0, m0); x1 = fmaxf(x1, m1);
        const float a0 = ex2(m0 - x0), a1 = ex2(m1 - x1);
        m0 = x0; m1 = x1; l0 *= a0; l1 *= a1;
#pragma unroll
        for (int n = 0; n < 16; n++) { O[4 * n] *= a0; O[4 * n + 1] *= a0; O[4 * n + 2] *= a1; O[4 * n + 3] *= a1; }
    }
    float s0 = 0.f, s1 = 0.f;
#pragma unroll
    for (int n = 0; n < 8; n++) {
        const float p0 = ex2(Sa[4 * n] - m0), p1 = ex2(Sa[4 * n + 1] - m0), p2 = ex2(Sa[4 * n + 2] - m1), p3 = ex2(Sa[4 * n + 3] - m1);
        s0 += p0 + p1; s1 += p2 + p3;
        P[2 * n] = pack_bf16(p0, p1); P[2 * n + 1] = pack_bf16(p2, p3);
    }
#pragma unroll
    for (int n = 0; n < 8; n++) {
        const float p0 = ex2(Sb[4 * n] - m0), p1 = ex2(Sb[4 * n + 1] - m0), p2 = ex2(Sb[4 * n + 2] - m1), p3 = ex2(Sb[4 * n + 3] - m1);
        s0 += p0 + p1; s1 += p2 + p3;
        P[16 + 2 * n] = pack_bf16(p0, p1); P[16 + 2 * n + 1] = pack_bf16(p2, p3);
    }
    l0 += s0; l1 += s1;
}

__device__ __forceinline__ void finish_sums(float l0, float l1, float& i0, float& i1) {
    l0 += __shfl_xor_sync(0xffffffffu, l0, 1);
    l1 += __shfl_xor_sync(0xffffffffu, l1, 1);
    l0 += __shfl_xor_sync(0xffffffffu, l0, 2);
    l1 += __shfl_xor_sync(0xffffffffu, l1, 2);
    asm("rcp.approx.ftz.f32 %0, %1;" : "=f"(i0) : "f"(l0));
    asm("rcp.approx.ftz.f32 %0, %1;" : "=f"(i1) : "f"(l1));
}
template <int H>
__device__ __forceinline__ void store_half(const float (&O)[64], float i0, float i1, __nv_bfloat16* __restrict__ out_row) {
#pragma unroll
    for (int c = 2 * H; c < 2 * H + 2; c++) {
        uint4 u, w;
        u.x = pack_bf16(O[16 * c + 0] * i0, O[16 * c + 1] * i0);
        u.y = pack_bf16(O[16 * c + 4] * i0, O[16 * c + 5] * i0);
        u.z = pack_bf16(O[16 * c + 8] * i0, O[16 * c + 9] * i0);
        u.w = pack_bf16(O[16 * c + 12] * i0, O[16 * c + 13] * i0);
        w.x = pack_bf16(O[16 * c + 2] * i1, O[16 * c + 3] * i1);
        w.y = pack_bf16(O[16 * c + 6] * i1, O[16 * c + 7] * i1);
        w.z = pack_bf16(O[16 * c + 10] * i1, O[16 * c + 11] * i1);
        w.w = pack_bf16(O[16 * c + 14] * i1, O[16 * c + 15] * i1);
        *reinterpret_cast<uint4*>(out_row + 32 * c) = u;
        *reinterpret_cast<uint4*>(out_row + 8 * DH + 32 * c) = w;
    }
}

__device__ __forceinline__ void load_q_frags(uint32_t (&Q)[32], uint32_t row_addr, uint32_t swz) {
#pragma unroll
    for (int k = 0; k < 8; k++)
        asm volatile("ldmatrix.sync.aligned.m8n8.x4.shared.b16 {%0, %1, %2, %3}, [%4];"
                     : "=r"(Q[4 * k]), "=r"(Q[4 * k + 1]), "=r"(Q[4 * k + 2]), "=r"(Q[4 * k + 3])
                     : "r"(row_addr + (k >> 2) * HALF_BYTES + (swz ^ ((k & 3) << 5))) : "memory");
}
template <int HALF>
__device__ __forceinline__ void issue_qk(float (&S)[32], const uint32_t (&Q)[32], uint64_t desc) {
#pragma unroll
    for (int k = 0; k < 8; k++)
        wgmma_n64_rs_kmajor(S, Q[4 * k], Q[4 * k + 1], Q[4 * k + 2], Q[4 * k + 3],
                            desc + (uint64_t)(HALF * (8192 >> 4) + (k >> 2) * (HALF_BYTES >> 4) + (k & 3) * 2), k > 0);
}
__device__ __forceinline__ void issue_pv(float (&O)[64], const uint32_t (&P)[32], uint64_t desc, int accumulate) {
#pragma unroll
    for (int k = 0; k < 8; k++)
        wgmma_n128_rs_mnmajor(O, P[4 * k], P[4 * k + 1], P[4 * k + 2], P[4 * k + 3],
                              desc + (uint64_t)(k * (2048 >> 4)), k > 0 ? 1 : accumulate);
}

__global__ void __launch_bounds__(384, 1)
attention_kernel(const __grid_constant__ CUtensorMap qmap, const __grid_constant__ TileOrder order,
                 const __grid_constant__ DequantArgs dq, const int natt, const int ninit, __nv_bfloat16* __restrict__ out) {
    extern __shared__ __align__(1024) uint8_t smem[];
    const uint32_t sb = smem_u32(smem);
    const int warp = __shfl_sync(0xffffffffu, threadIdx.x >> 5, 0), lane = threadIdx.x & 31;
    if ((int)blockIdx.x >= natt) {
        dequant_cta(dq, order, smem, sb, ninit + (blockIdx.x - natt), gridDim.x - natt, NTILES, warp, lane);
        return;
    }
    const int ntiles = (NQT - blockIdx.x + natt - 1) / natt;

    RawRows<4> R0;
    const int item = blockIdx.x * 3 + (warp - 1);
    const bool has_item = warp >= 1 && warp < 4 && item < ninit * TILE_DONE;
    const int item_f = has_item ? order.v[item >> 5] : 0;
    if (has_item) load_item(R0, dq, item_f, (item & 31) * 4, lane);
    const bool hold_q = (int)blockIdx.x * 3 < HOLD_Q_ITEMS;

    if (threadIdx.x == 0) {
        if (sb & 1023) __trap();
        for (int s = 0; s < STAGES; s++) {
            mbar_init(sb + BAR_FULLK + 8 * s, 1);
            mbar_init(sb + BAR_EMPTYK + 8 * s, 2);
            mbar_init(sb + BAR_FULLV + 8 * s, 1);
            mbar_init(sb + BAR_EMPTYV + 8 * s, 2);
        }
        mbar_init(sb + BAR_FULLQ, 1);
        mbar_init(sb + BAR_EMPTYQ, 8);
        asm volatile("fence.mbarrier_init.release.cluster;" ::: "memory");
    }
    __syncthreads();

    if (warp < 4) {
        asm volatile("setmaxnreg.dec.sync.aligned.u32 40;");
        if (warp == 0) {
            uint32_t st = 0, ph = 1, qph = 1;
            auto load_q = [&](int qt) {
                mbar_wait_trap(sb + BAR_EMPTYQ, qph);
                qph ^= 1;
                if (lane == 0) {
                    mbar_expect_tx(sb + BAR_FULLQ, TILE_BYTES);
                    tma_load_2d(sb + SM_Q, &qmap, 0, qt * 128, sb + BAR_FULLQ);
                    tma_load_2d(sb + SM_Q + HALF_BYTES, &qmap, 64, qt * 128, sb + BAR_FULLQ);
                }
                __syncwarp();
            };
            uint32_t ready = 0;
            int ready_head = -1;
            auto wait_tile = [&](int head, int bit) {
                uint32_t n = 0;
                while (!((ready >> bit) & 1)) {
                    uint32_t f;
                    asm volatile("ld.acquire.gpu.global.u32 %0, [%1];" : "=r"(f) : "l"(g_flags + head * 32 + lane) : "memory");
                    ready = __ballot_sync(0xffffffffu, f == TILE_DONE);
                    if ((ready >> bit) & 1) asm volatile("fence.proxy.async.global;" ::: "memory");
                    if (++n > (1u << 22)) __trap();
                }
            };
            if (hold_q) bar_sync(3, 128);
            load_q(blockIdx.x);
            for (int t = 0; t < ntiles; t++) {
                const int qt = blockIdx.x + t * natt;
                const int head = qt / QT_PER_HEAD;
                if (head != ready_head) { ready = 0; ready_head = head; }
                const uint8_t* kp = g_K + (size_t)head * NKT * TILE_BYTES;
                const uint8_t* vp = g_V + (size_t)head * NKT * TILE_BYTES;
                for (int j = 0; j < NKT; j++) {
                    wait_tile(head, 2 * j);
                    mbar_wait_trap(sb + BAR_EMPTYK + 8 * st, ph);
                    if (lane == 0) {
                        mbar_expect_tx(sb + BAR_FULLK + 8 * st, TILE_BYTES);
                        bulk_load(sb + SM_K + st * TILE_BYTES, kp + j * TILE_BYTES, TILE_BYTES, sb + BAR_FULLK + 8 * st);
                    }
                    wait_tile(head, 2 * j + 1);
                    mbar_wait_trap(sb + BAR_EMPTYV + 8 * st, ph);
                    if (lane == 0) {
                        mbar_expect_tx(sb + BAR_FULLV + 8 * st, TILE_BYTES);
                        bulk_load(sb + SM_V + st * TILE_BYTES, vp + j * TILE_BYTES, TILE_BYTES, sb + BAR_FULLV + 8 * st);
                    }
                    __syncwarp();
                    if (++st == STAGES) { st = 0; ph ^= 1; }
                    if (j == 4 && t + 1 < ntiles) load_q(qt + natt);
                }
            }
            uint32_t ticket = 0;
            if (lane == 0) ticket = atomicAdd(&g_done, 1u);
            ticket = __shfl_sync(0xffffffffu, ticket, 0);
            if (ticket == (uint32_t)natt - 1) {
#pragma unroll
                for (int i = 0; i < HKV; i++) g_flags[i * 32 + lane] = 0;
                if (lane == 0) g_done = 0;
            }
        } else {
            if (has_item) {
                store_item(R0, item_f, (item & 31) * 4, lane);
                __syncwarp();
                if (lane == 0) publish(g_flags + item_f, 1);
            }
            if (hold_q) bar_arrive(3, 128);
        }
    } else {
        asm volatile("setmaxnreg.inc.sync.aligned.u32 232;");
        const int wg = (warp >> 2) - 1, w = warp & 3;
        const int my_turn = 1 + wg, other_turn = 2 - wg;
        float O[64], Sa[32], Sb[32];
        uint32_t P[32], Q[32];
        float l0 = 0.f, l1 = 0.f, m0 = 0.f, m1 = 0.f;
        bool exact = false;
        uint32_t kst = 0, kph = 0, vst = 0, vph = 0, qph = 0;
        const uint64_t kdesc0 = make_desc(sb + SM_K, 16, 1024);
        const uint64_t vdesc0 = make_desc(sb + SM_V, HALF_BYTES, 1024);
        const uint32_t q_row = sb + SM_Q + (wg * 64 + w * 16 + (lane & 15)) * 128;
        const uint32_t q_swz = ((lane >> 4) ^ (lane & 7)) << 4;
        const bool releaser = (w == 0) && (lane == 0);
        const int row_in_cta = wg * 64 + w * 16 + (lane >> 2);

        auto load_q = [&]() {
            mbar_wait(sb + BAR_FULLQ, qph);
            qph ^= 1;
            load_q_frags(Q, q_row, q_swz);
            pin(Q);
            __syncwarp();
            if (lane == 0) mbar_arrive(sb + BAR_EMPTYQ);
        };
        auto release_k = [&]() {
            if (releaser) mbar_arrive(sb + BAR_EMPTYK + 8 * kst);
            if (++kst == STAGES) { kst = 0; kph ^= 1; }
        };
        auto release_v = [&]() {
            if (releaser) mbar_arrive(sb + BAR_EMPTYV + 8 * vst);
            if (++vst == STAGES) { vst = 0; vph ^= 1; }
        };
        bool v_ready = false, k_ready = false;
        auto lookahead = [&]() {
            const uint32_t nk = (kst + 1 == STAGES) ? 0 : kst + 1, nkph = (kst + 1 == STAGES) ? kph ^ 1 : kph;
            v_ready = mbar_test(sb + BAR_FULLV + 8 * vst, vph);
            k_ready = mbar_test(sb + BAR_FULLK + 8 * nk, nkph);
        };
        auto softmax = [&](auto first_tag) {
            constexpr bool FIRST = decltype(first_tag)::value;
            float a0 = 0.f, a1 = 0.f, b0 = 0.f, b1 = 0.f;
            if (FIRST) { exact = false; m0 = 0.f; m1 = 0.f; l0 = 0.f; l1 = 0.f; }
            const bool spec = !exact;
            if (spec) softmax_fast_half<0>(Sa, P, a0, a1, b0, b1);
            wg_wait<0>();
            pin(Sb); pin(Q);
            release_k();
            bool done = false;
            if (spec) {
                softmax_fast_half<16>(Sb, P, a0, a1, b0, b1);
                a0 += b0; a1 += b1;
                bool ok = (a0 <= SUM_HI) && (a1 <= SUM_HI);
                if (FIRST) ok = ok && (a0 >= SUM_LO) && (a1 >= SUM_LO);
                done = __all_sync(0xffffffffu, ok);
                if (done) { l0 += a0; l1 += a1; } else { exact = true; }
            }
            if (!done) softmax_exact<FIRST>(Sa, Sb, P, O, l0, l1, m0, m1);
        };
        struct True { enum { value = 1 }; };
        struct False { enum { value = 0 }; };

        if (wg == 1) bar_arrive(1, 256);
#pragma unroll
        for (int i = 0; i < 64; i++) asm volatile("" : "=f"(O[i]));

        load_q();
        mbar_wait(sb + BAR_FULLK + 8 * kst, kph);
        bar_sync(my_turn, 256);
        pin(Sa); pin(Sb); pin(Q);
        wg_fence();
        {
            const uint64_t kd = kdesc0 + (uint64_t)(kst * (TILE_BYTES >> 4));
            issue_qk<0>(Sa, Q, kd); wg_commit();
            issue_qk<1>(Sb, Q, kd); wg_commit();
        }
        bar_arrive(other_turn, 256);
        wg_wait<1>();
        pin(Sa);
        softmax(True{});

        for (int t = 0; t < ntiles; t++) {
#pragma unroll 1
            for (int j = 1; j < NKT; j++) {
                if (!v_ready) mbar_wait(sb + BAR_FULLV + 8 * vst, vph);
                if (!k_ready) mbar_wait(sb + BAR_FULLK + 8 * kst, kph);
                bar_sync(my_turn, 256);
                pin(Sa); pin(Sb); pin(O); pin(P); pin(Q);
                wg_fence();
                issue_pv(O, P, vdesc0 + (uint64_t)(vst * (TILE_BYTES >> 4)), j > 1);
                wg_commit();
                {
                    const uint64_t kd = kdesc0 + (uint64_t)(kst * (TILE_BYTES >> 4));
                    issue_qk<0>(Sa, Q, kd); wg_commit();
                    issue_qk<1>(Sb, Q, kd); wg_commit();
                }
                bar_arrive(other_turn, 256);
                wg_wait<1>();
                pin(O); pin(P); pin(Sa);
                release_v();
                lookahead();
                softmax(False{});
                pin(P);
            }
            const int qt = blockIdx.x + t * natt;
            __nv_bfloat16* out_row = out + (size_t)(qt * 128 + row_in_cta) * DH + 8 * (lane & 3);
            if (!v_ready) mbar_wait(sb + BAR_FULLV + 8 * vst, vph);
            float i0, i1;
            finish_sums(l0, l1, i0, i1);
            asm volatile("" : "+f"(i0), "+f"(i1)::"memory");
            if (t + 1 < ntiles) {
                if (!k_ready) mbar_wait(sb + BAR_FULLK + 8 * kst, kph);
                bar_sync(my_turn, 256);
                pin(Sa); pin(Sb); pin(O); pin(P);
                wg_fence();
                issue_pv(O, P, vdesc0 + (uint64_t)(vst * (TILE_BYTES >> 4)), 1);
                wg_commit();
                load_q();
                wg_fence();
                const uint64_t kd = kdesc0 + (uint64_t)(kst * (TILE_BYTES >> 4));
                issue_qk<0>(Sa, Q, kd); wg_commit();
                wg_wait<1>();
                pin(O); pin(P);
                release_v();
                store_half<0>(O, i0, i1, out_row);
                issue_qk<1>(Sb, Q, kd); wg_commit();
                bar_arrive(other_turn, 256);
                lookahead();
                store_half<1>(O, i0, i1, out_row);
                wg_wait<1>();
                pin(Sa);
                softmax(True{});
                pin(P);
            } else {
                bar_sync(my_turn, 256);
                pin(O); pin(P);
                wg_fence();
                issue_pv(O, P, vdesc0 + (uint64_t)(vst * (TILE_BYTES >> 4)), 1);
                wg_commit();
                if (wg == 0) bar_arrive(other_turn, 256);
                wg_wait<0>();
                pin(O); pin(P);
                store_half<0>(O, i0, i1, out_row);
                store_half<1>(O, i0, i1, out_row);
            }
        }
    }
}

}

typedef CUresult (*EncodeTiledFn)(CUtensorMap*, CUtensorMapDataType, cuuint32_t, void*, const cuuint64_t*, const cuuint64_t*,
                                  const cuuint32_t*, const cuuint32_t*, CUtensorMapInterleave, CUtensorMapSwizzle,
                                  CUtensorMapL2promotion, CUtensorMapFloatOOBfill);

extern "C" void kernel_launch(void* const* d_in, const int* in_sizes, int n_in, void* d_out, int out_size) {
    (void)in_sizes; (void)n_in; (void)out_size;
    static int grid = 0, natt = 0, ninit = 0;
    static EncodeTiledFn encode = nullptr;
    static TileOrder order;
    if (grid == 0) {
        cudaFuncSetAttribute(attention_kernel, cudaFuncAttributeMaxDynamicSharedMemorySize, SMEM_BYTES);
        int dev = 0, sms = 0;
        cudaGetDevice(&dev);
        cudaDeviceGetAttribute(&sms, cudaDevAttrMultiProcessorCount, dev);
        const int waves = (NQT + sms - 3) / (sms - 2);
        natt = (NQT + waves - 1) / waves;
        grid = sms < natt + 8 ? sms : natt + 8;
        ninit = (natt * 3) / TILE_DONE;
        int n = 0;
        for (int wave = 0; wave < waves; wave++)
            for (int slot = 0; slot <= NKT; slot++)
                for (int h = 0; h < HKV; h++) {
                    if ((h * QT_PER_HEAD) / natt != wave) continue;
                    if (slot < NKT) order.v[n++] = (uint8_t)((h * NKT + slot) * 2);
                    if (slot > 0) order.v[n++] = (uint8_t)((h * NKT + slot - 1) * 2 + 1);
                }
        void* fn = nullptr;
        cudaDriverEntryPointQueryResult qr;
        cudaGetDriverEntryPoint("cuTensorMapEncodeTiled", &fn, cudaEnableDefault, &qr);
        encode = (EncodeTiledFn)fn;
    }
    CUtensorMap qmap;
    const cuuint64_t dims[2] = {(cuuint64_t)DH, (cuuint64_t)HQ * SQ};
    const cuuint64_t strides[1] = {(cuuint64_t)DH * 2};
    const cuuint32_t box[2] = {64, 128};
    const cuuint32_t estr[2] = {1, 1};
    encode(&qmap, CU_TENSOR_MAP_DATA_TYPE_BFLOAT16, 2, d_in[0], dims, strides, box, estr, CU_TENSOR_MAP_INTERLEAVE_NONE,
           CU_TENSOR_MAP_SWIZZLE_128B, CU_TENSOR_MAP_L2_PROMOTION_L2_128B, CU_TENSOR_MAP_FLOAT_OOB_FILL_NONE);
    const DequantArgs dq = {(const int*)d_in[1], (const int*)d_in[2], (const __nv_bfloat16*)d_in[3], (const __nv_bfloat16*)d_in[4],
                            (const __nv_bfloat16*)d_in[5], (const __nv_bfloat16*)d_in[6]};
    attention_kernel<<<grid, 384, SMEM_BYTES>>>(qmap, order, dq, natt, ninit, (__nv_bfloat16*)d_out);
}
```
